```python
import torch

def _softmax(x, axis=-1):
    return torch.softmax(x, dim=axis)
def _gelu(x):
    return torch.nn.functional.gelu(x, approximate="tanh")
def _silu(x):
    return torch.nn.functional.silu(x)
def _sigmoid(x):
    return torch.sigmoid(x)
def _layernorm(x, axis=-1, eps=1e-5):
    m = x.mean(dim=axis, keepdim=True)
    v = x.var(dim=axis, keepdim=True, unbiased=False)
    return (x - m) / torch.sqrt(v + eps)
def _scatter_add(tgt, idx, src, axis=0):
    return tgt.clone().index_add_(axis, idx, src)
def _segment_sum(src, seg, n):
    out = torch.zeros((n,) + src.shape[1:], dtype=src.dtype)
    return out.index_add_(0, seg, src)
def _pad(x, pw):
    flat = tuple(v for pair in reversed(pw) for v in pair)
    return torch.nn.functional.pad(x, flat)

kernel_name = 'standalone__linear_kernel_rfa__decode'

def setup_inputs():

    _w = (lambda a: (lambda t: t.to(torch.bfloat16) if t.is_floating_point() else t)(torch.as_tensor(a)))
    B, H, Sq, Sk, D, M = 1, 16, 1, 32768, 256, 8
    return {
        "q": _w((lambda *s: torch.randn(*s, dtype=torch.bfloat16) * 0.4)(B, H, Sq, D)),
        "k": _w((lambda *s: torch.randn(*s, dtype=torch.bfloat16) * 1.6)(B, H, Sk, D)),
        "v": _w((lambda *s: torch.randn(*s, dtype=torch.bfloat16) * 1.6)(B, H, Sk, D)),
        "omega": _w((lambda *s: torch.randn(*s, dtype=torch.bfloat16) * 1.6)(M, D)),
    }

def reference(q, k, v, omega):
    d = q.shape[-1]
    m = omega.shape[0]
    scale = float(d) ** -0.25
    qs = q * scale
    ks = k * scale
    q_proj = torch.einsum("bhsd,md->bhsm", qs, omega)
    k_proj = torch.einsum("bhsd,md->bhsm", ks, omega)
    q_sq = 0.5 * torch.einsum("bhsd,bhsd->bhs", qs, qs)[..., None]
    k_sq = 0.5 * torch.einsum("bhsd,bhsd->bhs", ks, ks)[..., None]
    inv_sqrt_m = float(m) ** -0.5
    phi_q = torch.exp(q_proj - q_sq) * inv_sqrt_m + 1e-6
    phi_k = torch.exp(k_proj - k_sq) * inv_sqrt_m + 1e-6
    kv = torch.einsum("bhsm,bhsd->bhmd", phi_k, v)
    z  = torch.einsum("bhsm->bhm", phi_k)
    num = torch.einsum("bhqm,bhmd->bhqd", phi_q, kv)
    den = torch.einsum("bhqm,bhm->bhq", phi_q, z)[..., None] + 1e-6
    return num / den
```

```cpp
#include <cuda_runtime.h>
#include <cuda_bf16.h>
#include <cuda.h>
#include <stdint.h>

namespace rfa {

constexpr int kH = 16, kS = 32768, kD = 256;
constexpr int kTileKeys = 16;
constexpr int kTilesPerHead = kS / kTileKeys;
#define NWARPS 4
#define NREP 1
#define NSTATIC 2
#define PQ_ITER 4
#define DRY_ITER 6
constexpr int kWarps = NWARPS;
constexpr int kStatic = NSTATIC;
#define PLANAHEAD 320
#define HELPMARGIN 24
constexpr int kPlanAhead = PLANAHEAD;
constexpr int kHelpMargin = HELPMARGIN;
constexpr int kTileBytes = kTileKeys * kD * 2;
constexpr int kBufBytes = 2 * kTileBytes;
constexpr int kRep = NREP;
constexpr int kAccStride = 288;
constexpr int kOffQ = kWarps * kBufBytes;
constexpr int kOffOmega = kOffQ + kH * kD * 2;
constexpr int kOffPq = kOffOmega + 8 * kD * 2;
constexpr int kOffBar = kOffPq + kH * 8 * 4;
constexpr int kSmemBytes = kOffBar + 128 + 1024;

__device__ float g_acc[kH * kRep * kAccStride];
__device__ unsigned g_ctr[kH * 32];

__device__ __forceinline__ uint32_t smem_u32(const void* p) { return (uint32_t)__cvta_generic_to_shared(p); }

__device__ __forceinline__ void mbar_wait(uint32_t bar, uint32_t parity) {
    asm volatile(
        "{\n"
        ".reg .pred p;\n"
        "WAIT_LOOP:\n"
        "mbarrier.try_wait.parity.shared::cta.b64 p, [%0], %1;\n"
        "@p bra WAIT_DONE;\n"
        "bra WAIT_LOOP;\n"
        "WAIT_DONE:\n"
        "}\n" ::"r"(bar), "r"(parity) : "memory");
}

__device__ __forceinline__ void tma_tile(uint32_t dst, const CUtensorMap* tm, int row, uint32_t bar) {
    asm volatile(
        "cp.async.bulk.tensor.3d.shared::cluster.global.tile.mbarrier::complete_tx::bytes "
        "[%0], [%1, {%3, %4, %5}], [%2];" ::"r"(dst), "l"(tm), "r"(bar), "r"(0), "r"(row), "r"(0)
        : "memory");
}
__device__ __forceinline__ void prefetch_l2(const void* p, uint32_t bytes) {
    asm volatile("cp.async.bulk.prefetch.L2.global [%0], %1;" ::"l"(p), "r"(bytes) : "memory");
}

__device__ __forceinline__ void ldsm4(uint32_t& r0, uint32_t& r1, uint32_t& r2, uint32_t& r3, uint32_t addr) {
    asm volatile("ldmatrix.sync.aligned.m8n8.x4.shared.b16 {%0,%1,%2,%3}, [%4];"
                 : "=r"(r0), "=r"(r1), "=r"(r2), "=r"(r3) : "r"(addr) : "memory");
}
__device__ __forceinline__ void ldsm4t(uint32_t& r0, uint32_t& r1, uint32_t& r2, uint32_t& r3, uint32_t addr) {
    asm volatile("ldmatrix.sync.aligned.m8n8.x4.trans.shared.b16 {%0,%1,%2,%3}, [%4];"
                 : "=r"(r0), "=r"(r1), "=r"(r2), "=r"(r3) : "r"(addr) : "memory");
}
__device__ __forceinline__ void mma16816(float* c, uint32_t a0, uint32_t a1, uint32_t a2, uint32_t a3,
                                         uint32_t b0, uint32_t b1) {
    asm volatile(
        "mma.sync.aligned.m16n8k16.row.col.f32.bf16.bf16.f32 {%0,%1,%2,%3}, {%4,%5,%6,%7}, {%8,%9}, {%0,%1,%2,%3};"
        : "+f"(c[0]), "+f"(c[1]), "+f"(c[2]), "+f"(c[3])
        : "r"(a0), "r"(a1), "r"(a2), "r"(a3), "r"(b0), "r"(b1));
}
__device__ __forceinline__ float bf16r(float x) { return __bfloat162float(__float2bfloat16_rn(x)); }

__device__ __forceinline__ void phi_pair(const float* c, int lane, float& p0, float& p1) {
    const int t = lane & 3;
    const float diag = (lane & 4) ? c[3] : c[2];
    const float s0 = __shfl_sync(0xffffffffu, diag, 9 * t);
    const float s1 = __shfl_sync(0xffffffffu, diag, 9 * t + 4);
    const float x0 = bf16r(bf16r(c[0] * 0.25f) - bf16r(s0 * 0.03125f));
    const float x1 = bf16r(bf16r(c[1] * 0.25f) - bf16r(s1 * 0.03125f));
    const float inv_sqrt_m = 0.35355339059327373f;
    p0 = bf16r(bf16r(bf16r(expf(x0)) * inv_sqrt_m) + 1e-6f);
    p1 = bf16r(bf16r(bf16r(expf(x1)) * inv_sqrt_m) + 1e-6f);
}
__device__ __forceinline__ uint32_t pack_bf16(float lo, float hi) {
    return (__float_as_uint(lo) >> 16) | (__float_as_uint(hi) & 0xffff0000u);
}

__device__ __forceinline__ void query_features(const uint32_t* om_s, const uint32_t* q_s, float* pq, int lane) {
    const int g = lane >> 2, t = lane & 3;
    const uint32_t* om32 = om_s + g * 128 + t;
#pragma unroll 1
    for (int grp = 0; grp < 2; grp++) {
        const uint32_t* q32 = q_s + (8 * grp + g) * 128 + t;
        float c[4] = {0.f, 0.f, 0.f, 0.f};
#pragma unroll 2
        for (int s = 0; s < 16; s++) {
            const uint32_t b0 = q32[8 * s], b1 = q32[8 * s + 4];
            mma16816(c, om32[8 * s], b0, om32[8 * s + 4], b1, b0, b1);
        }
        float p0, p1;
        phi_pair(c, lane, p0, p1);
        pq[(8 * grp + 2 * t) * 8 + g] = p0;
        pq[(8 * grp + 2 * t + 1) * 8 + g] = p1;
    }
    __syncwarp();
}

__device__ __forceinline__ void fold_and_add(float (&acc)[16][4], float& z, int h, const float* pq, int lane,
                                             uint32_t live) {
    const int g = lane >> 2, t = lane & 3;
    const float pq0 = pq[h * 8 + 2 * t], pq1 = pq[h * 8 + 2 * t + 1], pqg = pq[h * 8 + g];
    float v[16][2];
#pragma unroll
    for (int b = 0; b < 16; b++) {
        v[b][0] = acc[b][0] * pq0 + acc[b][1] * pq1;
        v[b][1] = acc[b][2] * pq0 + acc[b][3] * pq1;
    }
    float w[8][2];
    const bool hi2 = lane & 2, hi1 = lane & 1;
#pragma unroll
    for (int b = 0; b < 8; b++)
#pragma unroll
        for (int j = 0; j < 2; j++) {
            const float send = hi2 ? v[b][j] : v[b + 8][j];
            const float keep = hi2 ? v[b + 8][j] : v[b][j];
            w[b][j] = keep + __shfl_xor_sync(0xffffffffu, send, 2);
        }
    float r[8];
#pragma unroll
    for (int b = 0; b < 4; b++)
#pragma unroll
        for (int j = 0; j < 2; j++) {
            const float send = hi1 ? w[b][j] : w[b + 4][j];
            const float keep = hi1 ? w[b + 4][j] : w[b][j];
            r[b * 2 + j] = keep + __shfl_xor_sync(0xffffffffu, send, 1);
        }
    float d = z * pqg;
#pragma unroll
    for (int o = 16; o > 0; o >>= 1) d += __shfl_xor_sync(0xffffffffu, d, o);

    float* a = g_acc + (h * kRep + (blockIdx.x % kRep)) * kAccStride;
    asm volatile(
        "{\n.reg .pred p, p0;\n"
        "setp.ne.u32 p, %11, 0;\n"
        "setp.ne.u32 p0, %12, 0;\n"
        "@p red.relaxed.gpu.global.add.v4.f32 [%0], {%2,%3,%4,%5};\n"
        "@p red.relaxed.gpu.global.add.v4.f32 [%0+16], {%6,%7,%8,%9};\n"
        "@p0 red.relaxed.gpu.global.add.f32 [%1], %10;\n"
        "}\n" ::"l"(a + lane * 8), "l"(a + 256), "f"(r[0]), "f"(r[1]), "f"(r[2]), "f"(r[3]), "f"(r[4]), "f"(r[5]),
        "f"(r[6]), "f"(r[7]), "f"(d), "r"(live), "r"(lane == 0 ? live : 0u) : "memory");
}

__device__ __forceinline__ bool commit_head(int h, int ntiles, int lane, uint32_t live) {
    __syncwarp();
    unsigned old = 1 - ntiles;
    asm volatile(
        "{\n.reg .pred p;\n"
        "setp.ne.u32 p, %3, 0;\n"
        "@p atom.acq_rel.gpu.global.add.u32 %0, [%1], %2;\n"
        "}\n" : "+r"(old) : "l"(g_ctr + h * 32 + 1), "r"(ntiles), "r"(lane == 0 ? live : 0u) : "memory");
    old = __shfl_sync(0xffffffffu, old, 0);
    return ((old + ntiles) & (kTilesPerHead - 1)) == 0;
}

__device__ __forceinline__ void finalize_head(int h, int lane, __nv_bfloat16* __restrict__ out, uint32_t live) {
    const int g = lane >> 2, t = lane & 3;
    float* a = g_acc + h * kRep * kAccStride;
    float n[8] = {0.f, 0.f, 0.f, 0.f, 0.f, 0.f, 0.f, 0.f};
    float dsum = 0.f;
#pragma unroll
    for (int rp = 0; rp < kRep; rp++) {
        float x[9] = {0.f, 0.f, 0.f, 0.f, 0.f, 0.f, 0.f, 0.f, 0.f};
        asm volatile(
            "{\n.reg .pred p;\n"
            "setp.ne.u32 p, %11, 0;\n"
            "@p ld.relaxed.gpu.global.v4.f32 {%0,%1,%2,%3}, [%9];\n"
            "@p ld.relaxed.gpu.global.v4.f32 {%4,%5,%6,%7}, [%9+16];\n"
            "@p ld.relaxed.gpu.global.f32 %8, [%10];\n"
            "}\n" : "+f"(x[0]), "+f"(x[1]), "+f"(x[2]), "+f"(x[3]), "+f"(x[4]), "+f"(x[5]), "+f"(x[6]), "+f"(x[7]),
            "+f"(x[8]) : "l"(a + rp * kAccStride + lane * 8), "l"(a + rp * kAccStride + 256), "r"(live) : "memory");
#pragma unroll
        for (int i = 0; i < 8; i++) n[i] += x[i];
        dsum += x[8];
    }
    const float rden = __frcp_rn(bf16r(bf16r(dsum) + 1e-6f));
#pragma unroll
    for (int i = 0; i < 8; i++) {
        const int dim = 16 * (4 * t + (i >> 1)) + 8 * (i & 1) + g;
        const unsigned short o = __bfloat16_as_ushort(__float2bfloat16_rn(bf16r(n[i]) * rden));
        asm volatile("{\n.reg .pred p;\nsetp.ne.u32 p, %2, 0;\n@p st.global.b16 [%0], %1;\n}\n" ::"l"(out + h * kD + dim),
                     "h"(o), "r"(live) : "memory");
    }
    __syncwarp();
#pragma unroll
    for (int rp = 0; rp < kRep; rp++) {
        asm volatile(
            "{\n.reg .pred p, p0;\n"
            "setp.ne.u32 p, %3, 0;\n"
            "setp.ne.u32 p0, %4, 0;\n"
            "@p st.global.v4.f32 [%0], {%2,%2,%2,%2};\n"
            "@p st.global.v4.f32 [%0+16], {%2,%2,%2,%2};\n"
            "@p0 st.global.f32 [%1], %2;\n"
            "}\n" ::"l"(a + rp * kAccStride + lane * 8), "l"(a + rp * kAccStride + 256), "f"(0.f), "r"(live),
            "r"(lane == 0 ? live : 0u) : "memory");
    }
}

__global__ void __launch_bounds__(kWarps * 32, 1)
rfa_decode_kernel(const __grid_constant__ CUtensorMap tmK, const __grid_constant__ CUtensorMap tmV,
                  const uint8_t* __restrict__ kptr, const uint8_t* __restrict__ vptr,
                  const __nv_bfloat16* __restrict__ q, const __nv_bfloat16* __restrict__ omega,
                  __nv_bfloat16* __restrict__ out, int dry_iter) {
    extern __shared__ uint8_t smem_raw[];
    const int lane = threadIdx.x & 31, warp = threadIdx.x >> 5;
    const int g = lane >> 2, t = lane & 3;
    const uint32_t sbase = (smem_u32(smem_raw) + 1023u) & ~1023u;
    const uint32_t kbuf = sbase + warp * kBufBytes;
    const uint32_t vbuf = kbuf + kTileBytes;
    uint8_t* sgen = smem_raw + (sbase - smem_u32(smem_raw));
    float* pq = reinterpret_cast<float*>(sgen + kOffPq);
    const uint32_t bar = sbase + kOffBar + warp * 8;
    const uint32_t bar_q = sbase + kOffBar + 64;
    const uint32_t bar_pq = bar_q + 8;

    const int nworkers = gridDim.x * kWarps;
    const int gw = blockIdx.x * kWarps + warp;
    int head = gw % kH;
    const int rank = gw / kH;
    const int nhome = (nworkers - head + kH - 1) / kH;

    if (lane == 0) {
        const int tile = head * kTilesPerHead + rank;
        asm volatile("mbarrier.init.shared::cta.b64 [%0], 1;" ::"r"(bar) : "memory");
        asm volatile("fence.mbarrier_init.release.cluster;" ::: "memory");
        asm volatile("fence.proxy.async.shared::cta;" ::: "memory");
        asm volatile("mbarrier.arrive.expect_tx.shared::cta.b64 _, [%0], %1;" ::"r"(bar), "r"(kBufBytes) : "memory");
        tma_tile(kbuf, &tmK, tile * kTileKeys, bar);
        tma_tile(vbuf, &tmV, tile * kTileKeys, bar);
        if (warp == 0) {
            asm volatile("mbarrier.init.shared::cta.b64 [%0], 1;" ::"r"(bar_q) : "memory");
            asm volatile("mbarrier.init.shared::cta.b64 [%0], 1;" ::"r"(bar_pq) : "memory");
            asm volatile("fence.mbarrier_init.release.cluster;" ::: "memory");
            asm volatile("fence.proxy.async.shared::cta;" ::: "memory");
            asm volatile("mbarrier.arrive.expect_tx.shared::cta.b64 _, [%0], %1;" ::"r"(bar_q), "r"(kOffPq - kOffQ) : "memory");
            asm volatile("cp.async.bulk.shared::cluster.global.mbarrier::complete_tx::bytes [%0], [%1], %2, [%3];" ::"r"(
                             sbase + kOffQ), "l"(q), "r"(kOffOmega - kOffQ), "r"(bar_q) : "memory");
            asm volatile("cp.async.bulk.shared::cluster.global.mbarrier::complete_tx::bytes [%0], [%1], %2, [%3];" ::"r"(
                             sbase + kOffOmega), "l"(omega), "r"(kOffPq - kOffOmega), "r"(bar_q) : "memory");
        }
    }
    __syncthreads();
    __syncwarp();

    uint32_t om[16][2];
    const uint32_t* om32 = reinterpret_cast<const uint32_t*>(omega);
#pragma unroll
    for (int s = 0; s < 16; s++) {
        om[s][0] = __ldg(om32 + g * 128 + 8 * s + t);
        om[s][1] = __ldg(om32 + g * 128 + 8 * s + 4 + t);
    }

    const int r = lane & 7, mi = lane >> 3;
    const uint32_t koff = kbuf + r * 128 + ((mi ^ r) << 4);
    const uint32_t voff = vbuf + ((mi >> 1) * 8 + r) * 128 + (((mi & 1) ^ r) << 4);

    float acc[16][4];
#pragma unroll
    for (int b = 0; b < 16; b++) acc[b][0] = acc[b][1] = acc[b][2] = acc[b][3] = 0.f;
    float z = 0.f;
    int ntiles = 0;
    int iter = 0;
    uint32_t parity = 0;
    bool have_pq = warp != 0;
    unsigned leave_order = 0;
    int idx = rank;
    bool planned = false;
    int lag = 0;

    while (true) {
        int nhead = head;
        if (iter < kStatic - 1) {
            idx = (iter + 1) * nhome + rank;
        } else {
            unsigned tk = 0;
            if (lane == 0) tk = atomicAdd(&g_ctr[head * 32], 1u);
            tk = __shfl_sync(0xffffffffu, tk, 0);
            idx = kStatic * ((nworkers - head + kH - 1) / kH) + (int)tk;
            if (!planned && idx >= kTilesPerHead - kPlanAhead) {
                planned = true;
                if (lane < kH) {
                    unsigned claimed;
                    asm volatile("ld.relaxed.gpu.global.u32 %0, [%1];" : "=r"(claimed) : "l"(g_ctr + lane * 32) : "memory");
                    lag = max(0, idx - kHelpMargin - (kStatic * ((nworkers - lane + kH - 1) / kH) + (int)claimed));
                }
            }
            if (idx >= kTilesPerHead) {
                if (lane == head) lag = 0;
                int pre = lag;
#pragma unroll
                for (int o = 1; o < kH; o <<= 1) {
                    const int u = __shfl_up_sync(0xffffffffu, pre, o);
                    if (lane >= o) pre += u;
                }
                const int total = __shfl_sync(0xffffffffu, pre, kH - 1);
                nhead = -1;
                if (total > 0) {
                    const uint32_t rnd = (gw + iter * 977u) * 0x9E3779B1u;
                    const int pick = (int)(((unsigned long long)(rnd >> 8) * (unsigned)total) >> 24);
                    const int cand = __ffs(__ballot_sync(0xffffffffu, lane < kH && pre > pick)) - 1;
                    if (lane == 0) tk = atomicAdd(&g_ctr[cand * 32], 1u);
                    tk = __shfl_sync(0xffffffffu, tk, 0);
                    idx = kStatic * ((nworkers - cand + kH - 1) / kH) + (int)tk;
                    if (idx < kTilesPerHead) nhead = cand;
                }
                if (nhead < 0 && lane == 0) leave_order = atomicInc(&g_ctr[2], nworkers - 1);
            }
        }

        mbar_wait(bar, parity);
        parity ^= 1;
        ntiles++;
        iter++;

        float c0[4] = {0.f, 0.f, 0.f, 0.f}, c1[4] = {0.f, 0.f, 0.f, 0.f};
        float c2[4] = {0.f, 0.f, 0.f, 0.f}, c3[4] = {0.f, 0.f, 0.f, 0.f};
#pragma unroll
        for (int j = 0; j < 8; j++) {
            const uint32_t a = (koff ^ ((j & 1) << 6)) + (j >> 1) * 2048;
            const int s = 2 * j;
            uint32_t r0, r1, r2, r3;
            ldsm4(r0, r1, r2, r3, a);
            mma16816(c0, om[s][0], r0, om[s][1], r1, r0, r1);
            mma16816(c1, om[s + 1][0], r2, om[s + 1][1], r3, r2, r3);
            ldsm4(r0, r1, r2, r3, a + 1024);
            mma16816(c2, om[s][0], r0, om[s][1], r1, r0, r1);
            mma16816(c3, om[s + 1][0], r2, om[s + 1][1], r3, r2, r3);
        }
#pragma unroll
        for (int i = 0; i < 4; i++) { c0[i] += c1[i]; c2[i] += c3[i]; }
        float p0, p1, p2, p3;
        phi_pair(c0, lane, p0, p1);
        phi_pair(c2, lane, p2, p3);
        z += (p0 + p1) + (p2 + p3);
        const uint32_t pb0 = pack_bf16(p0, p1), pb1 = pack_bf16(p2, p3);

#pragma unroll
        for (int b = 0; b < 16; b++) {
            uint32_t a0, a1, a2, a3;
            ldsm4t(a0, a1, a2, a3, (voff ^ ((b & 3) << 5)) + (b >> 2) * 2048);
            mma16816(acc[b], a0, a1, a2, a3, pb0, pb1);
        }

        if (nhead >= 0) {
            if (lane == 0) {
                asm volatile("mbarrier.arrive.expect_tx.shared::cta.b64 _, [%0], %1;" ::"r"(bar), "r"(kBufBytes) : "memory");
                tma_tile(kbuf, &tmK, (nhead * kTilesPerHead + idx) * kTileKeys, bar);
                tma_tile(vbuf, &tmV, (nhead * kTilesPerHead + idx) * kTileKeys, bar);
            }
            __syncwarp();
        }
        const bool leaving = nhead != head;
        if (!have_pq && (iter >= PQ_ITER || leaving)) {
            mbar_wait(bar_q, 0);
            query_features(reinterpret_cast<const uint32_t*>(sgen + kOffOmega), reinterpret_cast<const uint32_t*>(sgen + kOffQ),
                           pq, lane);
            if (lane == 0) asm volatile("mbarrier.arrive.shared::cta.b64 _, [%0];" ::"r"(bar_pq) : "memory");
            have_pq = true;
        }
        const bool dry = !leaving && warp == 0 && iter == dry_iter;
        if (!leaving && !dry) continue;
        const uint32_t live = leaving ? 1u : 0u;

        mbar_wait(bar_pq, 0);
        fold_and_add(acc, z, head, pq, lane, live);
        const bool last = commit_head(head, ntiles, lane, live);
        if (last || dry) finalize_head(head, lane, out, live);
        if (dry) continue;
        if (nhead < 0) break;
        head = nhead;
        ntiles = 0;
        z = 0.f;
#pragma unroll
        for (int b = 0; b < 16; b++) acc[b][0] = acc[b][1] = acc[b][2] = acc[b][3] = 0.f;
    }
    if (lane == 0 && leave_order == (unsigned)(nworkers - 1)) {
        for (int h = 0; h < kH; h++) g_ctr[h * 32] = 0;
    }
}

typedef CUresult (*EncodeTiledFn)(CUtensorMap*, CUtensorMapDataType, cuuint32_t, void*, const cuuint64_t*,
                                  const cuuint64_t*, const cuuint32_t*, const cuuint32_t*, CUtensorMapInterleave,
                                  CUtensorMapSwizzle, CUtensorMapL2promotion, CUtensorMapFloatOOBfill);

#define L2PROMO CU_TENSOR_MAP_L2_PROMOTION_NONE

static void make_map(EncodeTiledFn enc, CUtensorMap* tm, const void* ptr) {
    const cuuint64_t dims[3] = {64, (cuuint64_t)kH * kS, 4};
    const cuuint64_t strides[2] = {512, 128};
    const cuuint32_t box[3] = {64, kTileKeys, 4};
    const cuuint32_t estr[3] = {1, 1, 1};
    enc(tm, CU_TENSOR_MAP_DATA_TYPE_BFLOAT16, 3, const_cast<void*>(ptr), dims, strides, box, estr,
        CU_TENSOR_MAP_INTERLEAVE_NONE, CU_TENSOR_MAP_SWIZZLE_128B, L2PROMO, CU_TENSOR_MAP_FLOAT_OOB_FILL_NONE);
}

}

extern "C" void kernel_launch(void* const* d_in, const int* in_sizes, int n_in, void* d_out, int out_size) {
    using namespace rfa;
    (void)in_sizes; (void)n_in; (void)out_size;
    static EncodeTiledFn enc = nullptr;
    static int sms = 0;
    if (!enc) {
        void* fn = nullptr;
        cudaDriverEntryPointQueryResult st;
        cudaGetDriverEntryPoint("cuTensorMapEncodeTiled", &fn, cudaEnableDefault, &st);
        enc = (EncodeTiledFn)fn;
        int dev = 0;
        cudaGetDevice(&dev);
        cudaDeviceGetAttribute(&sms, cudaDevAttrMultiProcessorCount, dev);
        cudaFuncSetAttribute(rfa_decode_kernel, cudaFuncAttributeMaxDynamicSharedMemorySize, kSmemBytes);
    }
    CUtensorMap tmK, tmV;
    make_map(enc, &tmK, d_in[1]);
    make_map(enc, &tmV, d_in[2]);
    rfa_decode_kernel<<<sms, kWarps * 32, kSmemBytes, cudaStreamPerThread>>>(
        tmK, tmV, (const uint8_t*)d_in[1], (const uint8_t*)d_in[2], (const __nv_bfloat16*)d_in[0],
        (const __nv_bfloat16*)d_in[3], (__nv_bfloat16*)d_out, DRY_ITER);
}
```

```cpp
#include <cuda_runtime.h>
#include <cuda_bf16.h>
#include <cuda.h>
#include <stdint.h>

namespace rfa {

constexpr int kH = 16, kS = 32768, kD = 256;
constexpr int kTileKeys = 16;
constexpr int kTilesPerHead = kS / kTileKeys;
constexpr int kWarps = 3;
constexpr int kStatic = 2;
constexpr int kPqPass = 4;
constexpr int kTileBytes = kTileKeys * kD * 2;
constexpr int kOmegaStride = kD * 2 + 16;
constexpr int kOffQ = kWarps * 2 * kTileBytes;
constexpr int kOffOmega = kOffQ + kH * kD * 2;
constexpr int kOffPq = kOffOmega + 8 * kOmegaStride;
constexpr int kOffBar = kOffPq + kH * 8 * 4;
constexpr int kSmemBytes = kOffBar + kWarps * 16 + 16 + 1024;

__device__ float4 g_acc[kH * 128];
__device__ unsigned g_ticket[kH * 32];

__device__ __forceinline__ uint32_t smem_u32(const void* p) { return (uint32_t)__cvta_generic_to_shared(p); }

__device__ __forceinline__ void mbar_init(uint32_t bar) {
    asm volatile("mbarrier.init.shared::cta.b64 [%0], 1;" ::"r"(bar) : "memory");
}
__device__ __forceinline__ void mbar_expect(uint32_t bar, uint32_t bytes) {
    asm volatile("mbarrier.arrive.expect_tx.shared::cta.b64 _, [%0], %1;" ::"r"(bar), "r"(bytes) : "memory");
}
__device__ __forceinline__ void mbar_wait(uint32_t bar, uint32_t parity) {
    asm volatile(
        "{\n"
        ".reg .pred p;\n"
        "WAIT_LOOP:\n"
        "mbarrier.try_wait.parity.shared::cta.b64 p, [%0], %1;\n"
        "@p bra WAIT_DONE;\n"
        "bra WAIT_LOOP;\n"
        "WAIT_DONE:\n"
        "}\n" ::"r"(bar), "r"(parity) : "memory");
}
__device__ __forceinline__ bool elect_one() {
    uint32_t pred;
    asm volatile("{\n.reg .pred p;\nelect.sync _|p, 0xffffffff;\nselp.u32 %0, 1, 0, p;\n}\n" : "=r"(pred));
    return pred;
}
__device__ __forceinline__ void bulk_copy(uint32_t dst, const void* src, uint32_t bytes, uint32_t bar) {
    asm volatile("cp.async.bulk.shared::cluster.global.mbarrier::complete_tx::bytes [%0], [%1], %2, [%3];" ::"r"(dst),
                 "l"(src), "r"(bytes), "r"(bar) : "memory");
}
__device__ __forceinline__ void tma_tile(uint32_t dst, const CUtensorMap* tm, int row, uint32_t bar) {
    mbar_expect(bar, kTileBytes);
    asm volatile(
        "cp.async.bulk.tensor.3d.shared::cluster.global.tile.mbarrier::complete_tx::bytes "
        "[%0], [%1, {%3, %4, %5}], [%2];" ::"r"(dst), "l"(tm), "r"(bar), "r"(0), "r"(row), "r"(0)
        : "memory");
}

__device__ __forceinline__ void ldsm4(uint32_t& r0, uint32_t& r1, uint32_t& r2, uint32_t& r3, uint32_t addr) {
    asm volatile("ldmatrix.sync.aligned.m8n8.x4.shared.b16 {%0,%1,%2,%3}, [%4];"
                 : "=r"(r0), "=r"(r1), "=r"(r2), "=r"(r3) : "r"(addr) : "memory");
}
__device__ __forceinline__ void ldsm4t(uint32_t& r0, uint32_t& r1, uint32_t& r2, uint32_t& r3, uint32_t addr) {
    asm volatile("ldmatrix.sync.aligned.m8n8.x4.trans.shared.b16 {%0,%1,%2,%3}, [%4];"
                 : "=r"(r0), "=r"(r1), "=r"(r2), "=r"(r3) : "r"(addr) : "memory");
}
__device__ __forceinline__ void mma16816(float* c, uint32_t a0, uint32_t a1, uint32_t a2, uint32_t a3,
                                         uint32_t b0, uint32_t b1) {
    asm volatile(
        "mma.sync.aligned.m16n8k16.row.col.f32.bf16.bf16.f32 {%0,%1,%2,%3}, {%4,%5,%6,%7}, {%8,%9}, {%0,%1,%2,%3};"
        : "+f"(c[0]), "+f"(c[1]), "+f"(c[2]), "+f"(c[3])
        : "r"(a0), "r"(a1), "r"(a2), "r"(a3), "r"(b0), "r"(b1));
}

__device__ __forceinline__ uint32_t cvt_bf16x2(float lo, float hi) {
    uint32_t d;
    asm("cvt.rn.bf16x2.f32 %0, %1, %2;" : "=r"(d) : "f"(hi), "f"(lo));
    return d;
}
__device__ __forceinline__ float bf16_lo(uint32_t d) { return __uint_as_float(d << 16); }
__device__ __forceinline__ float bf16_hi(uint32_t d) { return __uint_as_float(d & 0xffff0000u); }
__device__ __forceinline__ void bf16r2(float& a, float& b) {
    const uint32_t d = cvt_bf16x2(a, b);
    a = bf16_lo(d);
    b = bf16_hi(d);
}

__device__ __forceinline__ uint32_t phi_pair(const float* c, int lane) {
    const int t = lane & 3;
    const float diag = (lane & 4) ? c[3] : c[2];
    float s0 = __shfl_sync(0xffffffffu, diag, 9 * t) * 0.03125f;
    float s1 = __shfl_sync(0xffffffffu, diag, 9 * t + 4) * 0.03125f;
    float a0 = c[0] * 0.25f, a1 = c[1] * 0.25f;
    bf16r2(a0, a1);
    bf16r2(s0, s1);
    float x0 = a0 - s0, x1 = a1 - s1;
    bf16r2(x0, x1);
    float e0 = expf(x0), e1 = expf(x1);
    bf16r2(e0, e1);
    e0 *= 0.35355339059327373f;
    e1 *= 0.35355339059327373f;
    bf16r2(e0, e1);
    return cvt_bf16x2(e0 + 1e-6f, e1 + 1e-6f);
}

__device__ __forceinline__ void query_features(const uint32_t* om_s, const uint32_t* q_s, float* pq, int lane) {
    const int g = lane >> 2, t = lane & 3;
    const uint32_t* om32 = om_s + g * (kOmegaStride / 4) + t;
#pragma unroll 1
    for (int grp = 0; grp < 2; grp++) {
        const uint32_t* q32 = q_s + (8 * grp + g) * 128 + t;
        float c[4] = {0.f, 0.f, 0.f, 0.f};
#pragma unroll 2
        for (int s = 0; s < 16; s++) {
            const uint32_t b0 = q32[8 * s], b1 = q32[8 * s + 4];
            mma16816(c, om32[8 * s], b0, om32[8 * s + 4], b1, b0, b1);
        }
        const uint32_t p = phi_pair(c, lane);
        pq[(8 * grp + 2 * t) * 8 + g] = bf16_lo(p);
        pq[(8 * grp + 2 * t + 1) * 8 + g] = bf16_hi(p);
    }
    __syncwarp();
}

__device__ __forceinline__ void v_product(float (&acc)[16][4], uint32_t voff, uint32_t pb0, uint32_t pb1) {
#pragma unroll
    for (int b = 0; b < 16; b++) {
        uint32_t a0, a1, a2, a3;
        ldsm4t(a0, a1, a2, a3, (voff ^ ((b & 3) << 5)) + (b >> 2) * 2048);
        mma16816(acc[b], a0, a1, a2, a3, pb0, pb1);
    }
}

__device__ __forceinline__ float warp_sum(float d) {
#pragma unroll
    for (int o = 16; o > 0; o >>= 1) d += __shfl_xor_sync(0xffffffffu, d, o);
    return d;
}

__device__ __forceinline__ void publish(const float (&acc)[16][4], float den, float pq0, float pq1, float4* a,
                                        int nhome, __nv_bfloat16* __restrict__ out_row, int lane) {
    float v[16][2];
#pragma unroll
    for (int b = 0; b < 16; b++) {
        v[b][0] = acc[b][0] * pq0 + acc[b][1] * pq1;
        v[b][1] = acc[b][2] * pq0 + acc[b][3] * pq1;
    }
    float w[8][2];
    const bool hi2 = lane & 2, hi1 = lane & 1;
#pragma unroll
    for (int b = 0; b < 8; b++)
#pragma unroll
        for (int j = 0; j < 2; j++) {
            const float send = hi2 ? v[b][j] : v[b + 8][j];
            const float keep = hi2 ? v[b + 8][j] : v[b][j];
            w[b][j] = keep + __shfl_xor_sync(0xffffffffu, send, 2);
        }
    float r[4][2], old[4][4];
#pragma unroll
    for (int b = 0; b < 4; b++) {
#pragma unroll
        for (int j = 0; j < 2; j++) {
            const float send = hi1 ? w[b][j] : w[b + 4][j];
            const float keep = hi1 ? w[b + 4][j] : w[b][j];
            r[b][j] = keep + __shfl_xor_sync(0xffffffffu, send, 1);
        }
        asm volatile("atom.relaxed.gpu.global.add.v4.f32 {%0,%1,%2,%3}, [%4], {%5,%6,%7,%8};"
                     : "=f"(old[b][0]), "=f"(old[b][1]), "=f"(old[b][2]), "=f"(old[b][3])
                     : "l"(a + b * 32 + lane), "f"(r[b][0]), "f"(r[b][1]), "f"(den), "f"(1.0f) : "memory");
    }
    const float complete = (float)(nhome - 1);
    __nv_bfloat16* o = out_row + 64 * (lane & 3) + (lane >> 2);
#pragma unroll
    for (int b = 0; b < 4; b++) {
        float n0 = old[b][0] + r[b][0], n1 = old[b][1] + r[b][1];
        bf16r2(n0, n1);
        const float d0 = bf16_lo(cvt_bf16x2(old[b][2] + den, 0.f));
        const float d1 = bf16_lo(cvt_bf16x2(d0 + 1e-6f, 0.f));
        float rden;
        asm("rcp.approx.f32 %0, %1;" : "=f"(rden) : "f"(d1));
        const uint32_t res = cvt_bf16x2(n0 * rden, n1 * rden);
        asm volatile(
            "{\n.reg .pred p;\n.reg .b16 l, h;\n"
            "setp.eq.f32 p, %3, %4;\n"
            "mov.b32 {l, h}, %2;\n"
            "@p st.global.b16 [%0], l;\n"
            "@p st.global.b16 [%0+16], h;\n"
            "@p st.global.v4.f32 [%1], {%5,%5,%5,%5};\n"
            "}\n" ::"l"(o + 16 * b), "l"(a + b * 32 + lane), "r"(res), "f"(old[b][3]), "f"(complete), "f"(0.f) : "memory");
    }
}

__global__ void __launch_bounds__(kWarps * 32, 1)
rfa_decode_kernel(const __grid_constant__ CUtensorMap tmK, const __grid_constant__ CUtensorMap tmV,
                  const __nv_bfloat16* __restrict__ q, const __nv_bfloat16* __restrict__ omega,
                  __nv_bfloat16* __restrict__ out, unsigned* tickets, float4* accs, uint32_t zero) {
    extern __shared__ uint8_t smem_raw[];
    const int lane = threadIdx.x & 31;
    const int warp = __shfl_sync(0xffffffffu, threadIdx.x >> 5, 0);
    const uint32_t sbase = (smem_u32(smem_raw) + 1023u) & ~1023u;
    const uint32_t kbuf = sbase + warp * 2 * kTileBytes;
    const uint32_t vbuf = kbuf + kTileBytes;
    const uint32_t bar_k = sbase + kOffBar + warp * 16;
    const uint32_t bar_v = bar_k + 8;

    const int gw = blockIdx.x * kWarps + warp;
    const int head = gw % kH;
    const int rank = gw / kH;
    const int row0 = head * kS;

    if (elect_one()) {
        mbar_init(bar_k);
        tma_tile(kbuf, &tmK, row0 + rank * kTileKeys, bar_k);
        mbar_init(bar_v);
        tma_tile(vbuf, &tmV, row0 + rank * kTileKeys, bar_v);
    }
    const uint32_t bar_q = sbase + kOffBar + kWarps * 16;
    const uint32_t bar_pq = bar_q + 8;
    {
        constexpr int kThreads = kWarps * 32, kPer = (256 + kThreads - 1) / kThreads;
        uint4 x[kPer];
#pragma unroll
        for (int i = 0; i < kPer; i++) {
            const int c = threadIdx.x + i * kThreads;
            if (c < 256)
                asm volatile("ld.global.nc.v4.u32 {%0,%1,%2,%3}, [%4];" : "=r"(x[i].x), "=r"(x[i].y), "=r"(x[i].z), "=r"(x[i].w)
                             : "l"(reinterpret_cast<const uint4*>(omega) + c));
        }
        if (threadIdx.x == 0) {
            mbar_init(bar_q);
            mbar_init(bar_pq);
        }
#pragma unroll
        for (int i = 0; i < kPer; i++) {
            const int c = threadIdx.x + i * kThreads;
            if (c < 256)
                asm volatile("st.shared.v4.u32 [%0], {%1,%2,%3,%4};" ::"r"(sbase + kOffOmega + (c >> 5) * kOmegaStride + (c & 31) * 16),
                             "r"(x[i].x), "r"(x[i].y), "r"(x[i].z), "r"(x[i].w) : "memory");
        }
    }
    __syncthreads();

    const int g = lane >> 2, t = lane & 3;
    const int nhome = (gridDim.x * kWarps - head + kH - 1) / kH;
    const unsigned ndraws = kTilesPerHead - (kStatic - 1) * nhome;
    uint8_t* sgen = smem_raw + (sbase - smem_u32(smem_raw));
    float* pq = reinterpret_cast<float*>(sgen + kOffPq);

    uint32_t om[16][2];
#pragma unroll
    for (int s = 0; s < 16; s += 2)
        ldsm4(om[s][0], om[s][1], om[s + 1][0], om[s + 1][1],
              sbase + kOffOmega + (lane & 7) * kOmegaStride + (2 * s + (lane >> 3)) * 16);

    const int r = lane & 7, mi = lane >> 3;
    const uint32_t koff = kbuf + r * 128 + ((mi ^ r) << 4);
    const uint32_t voff = vbuf + ((mi >> 1) * 8 + r) * 128 + (((mi & 1) ^ r) << 4);

    float acc[16][4];
#pragma unroll
    for (int b = 0; b < 16; b++) acc[b][0] = acc[b][1] = acc[b][2] = acc[b][3] = 0.f;
    float z = 0.f;
    uint32_t pb0 = 0, pb1 = 0;
    float pq0 = 0.f, pq1 = 0.f, pqg = 0.f;
    int pq_state = warp == 0 ? 0 : 1;

    int nidx = rank;
    uint32_t par_k = 0, par_v = 0;
    for (int iter = 0;; iter++) {
        const bool draw = iter >= kStatic - 1;
        unsigned tk = 0;
        if (draw && lane == 0) tk = atomicInc(tickets + head * 32, ndraws - 1);

        if (iter > 0) {
            mbar_wait(bar_v, par_v);
            par_v ^= 1;
            v_product(acc, voff, pb0, pb1);
            if (elect_one()) {
                tma_tile(vbuf, &tmV, row0 + nidx * kTileKeys, bar_v);
                if (warp == 0 && iter == 1) {
                    mbar_expect(bar_q, kH * kD * 2);
                    bulk_copy(sbase + kOffQ, q, kH * kD * 2, bar_q);
                }
            }
            __syncwarp();

            if (pq_state == 0 && iter >= kPqPass) {
                mbar_wait(bar_q, 0);
                query_features(reinterpret_cast<const uint32_t*>(sgen + kOffOmega),
                               reinterpret_cast<const uint32_t*>(sgen + kOffQ), pq, lane);
                if (lane == 0) asm volatile("mbarrier.arrive.shared::cta.b64 _, [%0];" ::"r"(bar_pq) : "memory");
                pq_state = 1;
            } else if (pq_state == 1 && iter >= kPqPass + 4) {
                mbar_wait(bar_pq, 0);
                pq0 = pq[head * 8 + 2 * t];
                pq1 = pq[head * 8 + 2 * t + 1];
                pqg = pq[head * 8 + g];
                pq_state = 2;
            }
        }

        mbar_wait(bar_k, par_k);
        par_k ^= 1;
        float c0[4] = {0.f, 0.f, 0.f, 0.f}, c1[4] = {0.f, 0.f, 0.f, 0.f};
        float c2[4] = {0.f, 0.f, 0.f, 0.f}, c3[4] = {0.f, 0.f, 0.f, 0.f};
#pragma unroll
        for (int j = 0; j < 8; j++) {
            const uint32_t a = (koff ^ ((j & 1) << 6)) + (j >> 1) * 2048;
            const int s = 2 * j;
            uint32_t r0, r1, r2, r3;
            ldsm4(r0, r1, r2, r3, a);
            mma16816(c0, om[s][0], r0, om[s][1], r1, r0, r1);
            mma16816(c1, om[s + 1][0], r2, om[s + 1][1], r3, r2, r3);
            ldsm4(r0, r1, r2, r3, a + 1024);
            mma16816(c2, om[s][0], r0, om[s][1], r1, r0, r1);
            mma16816(c3, om[s + 1][0], r2, om[s + 1][1], r3, r2, r3);
        }
        tk = __shfl_sync(0xffffffffu, tk + (__float_as_uint(c3[0]) & zero), 0);
        const int cidx = draw ? kStatic * nhome + (int)tk : (iter + 1) * nhome + rank;
        if (cidx < kTilesPerHead && elect_one()) tma_tile(kbuf, &tmK, row0 + cidx * kTileKeys, bar_k);
        __syncwarp();
#pragma unroll
        for (int i = 0; i < 4; i++) { c0[i] += c1[i]; c2[i] += c3[i]; }
        pb0 = phi_pair(c0, lane);
        pb1 = phi_pair(c2, lane);
        z += (bf16_lo(pb0) + bf16_hi(pb0)) + (bf16_lo(pb1) + bf16_hi(pb1));
        if (cidx >= kTilesPerHead) break;
        nidx = cidx;
    }

    if (pq_state != 2) {
        if (pq_state == 0) {
            mbar_wait(bar_q, 0);
            query_features(reinterpret_cast<const uint32_t*>(sgen + kOffOmega),
                           reinterpret_cast<const uint32_t*>(sgen + kOffQ), pq, lane);
            if (lane == 0) asm volatile("mbarrier.arrive.shared::cta.b64 _, [%0];" ::"r"(bar_pq) : "memory");
        }
        mbar_wait(bar_pq, 0);
        pq0 = pq[head * 8 + 2 * t];
        pq1 = pq[head * 8 + 2 * t + 1];
        pqg = pq[head * 8 + g];
    }
    const float den = warp_sum(z * pqg);
    mbar_wait(bar_v, par_v);
    v_product(acc, voff, pb0, pb1);
    publish(acc, den, pq0, pq1, accs + head * 128, nhome, out + head * kD, lane);
}

typedef CUresult (*EncodeTiledFn)(CUtensorMap*, CUtensorMapDataType, cuuint32_t, void*, const cuuint64_t*,
                                  const cuuint64_t*, const cuuint32_t*, const cuuint32_t*, CUtensorMapInterleave,
                                  CUtensorMapSwizzle, CUtensorMapL2promotion, CUtensorMapFloatOOBfill);

static void make_map(EncodeTiledFn enc, CUtensorMap* tm, const void* ptr) {
    const cuuint64_t dims[3] = {64, (cuuint64_t)kH * kS, 4};
    const cuuint64_t strides[2] = {512, 128};
    const cuuint32_t box[3] = {64, kTileKeys, 4};
    const cuuint32_t estr[3] = {1, 1, 1};
    enc(tm, CU_TENSOR_MAP_DATA_TYPE_BFLOAT16, 3, const_cast<void*>(ptr), dims, strides, box, estr,
        CU_TENSOR_MAP_INTERLEAVE_NONE, CU_TENSOR_MAP_SWIZZLE_128B, CU_TENSOR_MAP_L2_PROMOTION_NONE,
        CU_TENSOR_MAP_FLOAT_OOB_FILL_NONE);
}

}

extern "C" void kernel_launch(void* const* d_in, const int* in_sizes, int n_in, void* d_out, int out_size) {
    using namespace rfa;
    (void)in_sizes; (void)n_in; (void)out_size;
    static EncodeTiledFn enc = nullptr;
    static int grid = 0;
    static void *tickets = nullptr, *accs = nullptr;
    if (!enc) {
        void* fn = nullptr;
        cudaDriverEntryPointQueryResult st;
        cudaGetDriverEntryPoint("cuTensorMapEncodeTiled", &fn, cudaEnableDefault, &st);
        enc = (EncodeTiledFn)fn;
        int dev = 0, sms = 0;
        cudaGetDevice(&dev);
        cudaDeviceGetAttribute(&sms, cudaDevAttrMultiProcessorCount, dev);
        grid = sms;
        while (grid > 1 && (grid * kWarps) % kH) grid--;
        if (grid * kWarps < kH) grid = (kH + kWarps - 1) / kWarps;
        cudaFuncSetAttribute(rfa_decode_kernel, cudaFuncAttributeMaxDynamicSharedMemorySize, kSmemBytes);
        cudaGetSymbolAddress(&tickets, g_ticket);
        cudaGetSymbolAddress(&accs, g_acc);
    }
    CUtensorMap tmK, tmV;
    make_map(enc, &tmK, d_in[1]);
    make_map(enc, &tmV, d_in[2]);
    rfa_decode_kernel<<<grid, kWarps * 32, kSmemBytes, cudaStreamPerThread>>>(
        tmK, tmV, (const __nv_bfloat16*)d_in[0], (const __nv_bfloat16*)d_in[3], (__nv_bfloat16*)d_out,
        (unsigned*)tickets, (float4*)accs, 0u);
}
```
